```python
import torch

def _softmax(x, axis=-1):
    return torch.softmax(x, dim=axis)

def _gelu(x):
    return torch.nn.functional.gelu(x, approximate='tanh')

def _silu(x):
    return torch.nn.functional.silu(x)

def _sigmoid(x):
    return torch.sigmoid(x)

def _layernorm(x, axis=-1, eps=1e-05):
    m = x.mean(dim=axis, keepdim=True)
    v = x.var(dim=axis, keepdim=True, unbiased=False)
    return (x - m) / torch.sqrt(v + eps)

def _scatter_add(tgt, idx, src, axis=0):
    return tgt.clone().index_add_(axis, idx, src)

def _segment_sum(src, seg, n):
    out = torch.zeros((n,) + src.shape[1:], dtype=src.dtype)
    return out.index_add_(0, seg, src)

def _pad(x, pw):
    flat = tuple((v for pair in reversed(pw) for v in pair))
    return torch.nn.functional.pad(x, flat)
kernel_name = 'standalone__autoregressive_conv_wavernn__speech'

def setup_inputs():

    _w = lambda a: (lambda t: t.to(torch.bfloat16) if t.is_floating_point() else t)(torch.as_tensor(a))
    B, T, D, K = (2, 1000, 512, 15)
    return {'x': _w((lambda *s: torch.randn(*s, dtype=torch.bfloat16) * 0.05)(B, T, D)), 'w': _w((lambda *s: torch.randn(*s, dtype=torch.bfloat16) * 0.05)(K, D, 2 * D))}

def reference(x, w):
    B, T, D = x.shape
    K = w.shape[0]
    dil = 2
    pad = (K - 1) * dil
    xp = _pad(x, ((0, 0), (pad, 0), (0, 0)))
    h = torch.einsum('btd,de->bte', xp[:, 0:T, :], w[0])
    for i in range(1, K):
        h = h + torch.einsum('btd,de->bte', xp[:, i * dil:i * dil + T, :], w[i])
    f, g = (h[..., :D].clone(), h[..., D:].clone())
    return torch.tanh(f) * _sigmoid(g)
```

```cpp
#include <cuda_runtime.h>
#include <cuda_bf16.h>
#include <cuda.h>
#include <stdint.h>

namespace {

constexpr int T_LEN = 1000, DCH = 512;
constexpr int TRI = 84;
constexpr int AROWS = 96;
constexpr int ABYTES = AROWS * 64;
constexpr int XABYTES = 5 * ABYTES;
constexpr int WABYTES = 36864, WBBYTES = 24576, WCBYTES = WABYTES + WBBYTES;
constexpr int NCHUNK = 16;
constexpr int RBOX2 = 144;
constexpr int EXBYTES = 2 * RBOX2 * 128;
constexpr int EP = 80;
constexpr int OFF_W = 2 * XABYTES;
constexpr int OFF_E = OFF_W + 2 * WCBYTES;
constexpr int OFF_B = OFF_E + EXBYTES;
constexpr int SMEM_BYTES = OFF_B + 256;
constexpr uint32_t SB = 1024;
__host__ __device__ constexpr uint32_t wtile(int p, int tap) { return OFF_W + p * WCBYTES + (tap < 9 ? tap * 2048 : WABYTES + (tap - 9) * 2048); }
__host__ __device__ constexpr uint32_t desc_a(int p, int tap, int kk) { return (((tap < 9 ? 18432u : 12288u) >> 4) << 16) | ((SB + wtile(p, tap) + kk * 1024) >> 4); }
__host__ __device__ constexpr uint32_t desc_b(uint32_t off) { return (1u << 16) | ((SB + off) >> 4); }
static_assert(SMEM_BYTES <= 232448, "smem");

constexpr int GRP_BYTES = 512 * 1024;
__device__ __align__(1024) uint8_t g_scratch[8 * GRP_BYTES + 2 * 1024 * 1024];

__device__ __forceinline__ uint32_t smem_u32(const void* p) { return (uint32_t)__cvta_generic_to_shared(p); }
__device__ __forceinline__ void mbar_init(uint32_t bar, uint32_t cnt) { asm volatile("mbarrier.init.shared::cta.b64 [%0], %1;" ::"r"(bar), "r"(cnt)); }
__device__ __forceinline__ void mbar_expect_tx(uint32_t bar, uint32_t bytes) { asm volatile("mbarrier.arrive.expect_tx.shared::cta.b64 _, [%0], %1;" ::"r"(bar), "r"(bytes) : "memory"); }
__device__ __forceinline__ void mbar_arrive(uint32_t bar) { asm volatile("mbarrier.arrive.shared::cta.b64 _, [%0];" ::"r"(bar) : "memory"); }
__device__ __forceinline__ void mbar_arrive_addr(uint32_t cluster_addr) {
    asm volatile("mbarrier.arrive.shared::cluster.b64 _, [%0];" ::"r"(cluster_addr) : "memory");
}
__device__ __forceinline__ uint32_t mbar_try(uint32_t bar, uint32_t parity) {
    uint32_t ok;
    asm volatile("{\n.reg .pred p;\nmbarrier.test_wait.parity.shared::cta.b64 p, [%1], %2;\nselp.u32 %0, 1, 0, p;\n}" : "=r"(ok) : "r"(bar), "r"(parity) : "memory");
    return ok;
}
__device__ __forceinline__ void mbar_wait(uint32_t bar, uint32_t parity) {
    asm volatile(
        "{\n.reg .pred p;\n.reg .u32 n;\n"
        "mbarrier.try_wait.parity.shared::cta.b64 p, [%0], %1;\n"
        "@p bra DONE_%=;\n"
        "mov.u32 n, 0;\n"
        "LOOP_%=:\n"
        "mbarrier.try_wait.parity.shared::cta.b64 p, [%0], %1;\n"
        "@p bra DONE_%=;\n"
        "add.u32 n, n, 1;\n"
        "setp.lt.u32 p, n, 1048576;\n"
        "@p bra LOOP_%=;\n"
        "trap;\n"
        "DONE_%=:\n}"
        ::"r"(bar), "r"(parity) : "memory");
}
__device__ __forceinline__ void mbar_wait_fast(uint32_t bar, uint32_t parity) {
    if (__builtin_expect(!mbar_try(bar, parity), 0)) mbar_wait(bar, parity);
}
__device__ __forceinline__ void mbar_wait_fast2(uint32_t bar0, uint32_t bar1, uint32_t parity) {
    const uint32_t ok0 = mbar_try(bar0, parity), ok1 = mbar_try(bar1, parity);
    if (__builtin_expect(!(ok0 & ok1), 0)) { mbar_wait(bar0, parity); mbar_wait(bar1, parity); }
}
__device__ __forceinline__ bool elect_one() {
    uint32_t p;
    asm volatile("{\n.reg .pred p;\nelect.sync _|p, 0xffffffff;\nselp.u32 %0, 1, 0, p;\n}" : "=r"(p));
    return p;
}
__device__ __forceinline__ void tma_3d_mc(uint32_t dst, const CUtensorMap* tm, int c0, int c1, int c2, uint32_t bar, uint16_t mask) {
    asm volatile("cp.async.bulk.tensor.3d.shared::cluster.global.mbarrier::complete_tx::bytes.multicast::cluster [%0], [%1, {%3, %4, %5}], [%2], %6;"
                 ::"r"(dst), "l"(tm), "r"(bar), "r"(c0), "r"(c1), "r"(c2), "h"(mask) : "memory");
}
__device__ __forceinline__ void tma_3d(uint32_t dst, const CUtensorMap* tm, int c0, int c1, int c2, uint32_t bar) {
    asm volatile("cp.async.bulk.tensor.3d.shared::cluster.global.mbarrier::complete_tx::bytes [%0], [%1, {%3, %4, %5}], [%2];"
                 ::"r"(dst), "l"(tm), "r"(bar), "r"(c0), "r"(c1), "r"(c2) : "memory");
}
__device__ __forceinline__ void tma_4d(uint32_t dst, const CUtensorMap* tm, int c0, int c1, int c2, int c3, uint32_t bar) {
    asm volatile("cp.async.bulk.tensor.4d.shared::cluster.global.mbarrier::complete_tx::bytes [%0], [%1, {%3, %4, %5, %6}], [%2];"
                 ::"r"(dst), "l"(tm), "r"(bar), "r"(c0), "r"(c1), "r"(c2), "r"(c3) : "memory");
}
__device__ __forceinline__ void flag_wait(const unsigned int* p, unsigned int want) {
    asm volatile(
        "{\n.reg .pred p;\n.reg .u32 n, v;\n.reg .s32 d;\n"
        "mov.u32 n, 0;\n"
        "LOOP_%=:\n"
        "ld.acquire.gpu.global.u32 v, [%0];\n"
        "sub.s32 d, v, %1;\n"
        "setp.ge.s32 p, d, 0;\n"
        "@p bra DONE_%=;\n"
        "add.u32 n, n, 1;\n"
        "setp.lt.u32 p, n, 1048576;\n"
        "@p bra LOOP_%=;\n"
        "trap;\n"
        "DONE_%=:\n}"
        ::"l"(p), "r"(want) : "memory");
}
__device__ __forceinline__ void bulk_load(uint32_t dst, const void* src, uint32_t bytes, uint32_t bar) {
    asm volatile("cp.async.bulk.shared::cluster.global.mbarrier::complete_tx::bytes [%0], [%1], %2, [%3];"
                 ::"r"(dst), "l"(src), "r"(bytes), "r"(bar) : "memory");
}
__device__ __forceinline__ void wgmma_fence() { asm volatile("wgmma.fence.sync.aligned;" ::: "memory"); }
__device__ __forceinline__ void wgmma_commit() { asm volatile("wgmma.commit_group.sync.aligned;" ::: "memory"); }
template <int N> __device__ __forceinline__ void wgmma_wait() { asm volatile("wgmma.wait_group.sync.aligned %0;" ::"n"(N) : "memory"); }
__device__ __forceinline__ void ldsm4t(uint32_t (&r)[4], uint32_t addr) {
    asm volatile("ldmatrix.sync.aligned.m8n8.x4.trans.shared.b16 {%0,%1,%2,%3}, [%4];" : "=r"(r[0]), "=r"(r[1]), "=r"(r[2]), "=r"(r[3]) : "r"(addr) : "memory");
}
__device__ __forceinline__ void stsm4t(uint32_t addr, uint32_t r0, uint32_t r1, uint32_t r2, uint32_t r3) {
    asm volatile("stmatrix.sync.aligned.m8n8.x4.trans.shared.b16 [%0], {%1,%2,%3,%4};" ::"r"(addr), "r"(r0), "r"(r1), "r"(r2), "r"(r3) : "memory");
}
__device__ __forceinline__ uint4 lds128(uint32_t addr) {
    uint4 v; asm volatile("ld.shared.v4.u32 {%0,%1,%2,%3}, [%4];" : "=r"(v.x), "=r"(v.y), "=r"(v.z), "=r"(v.w) : "r"(addr) : "memory"); return v;
}
__device__ __forceinline__ void sts128(uint32_t addr, uint32_t a, uint32_t b, uint32_t c, uint32_t d) {
    asm volatile("st.shared.v4.u32 [%0], {%1,%2,%3,%4};" ::"r"(addr), "r"(a), "r"(b), "r"(c), "r"(d) : "memory");
}
__device__ __forceinline__ void wgmma_ss_n88(float (&d)[44], uint32_t da, uint32_t db, uint32_t acc = 1) {
    asm volatile("{\n.reg .b64 da, db;\n.reg .pred p;\nsetp.ne.u32 p, %46, 0;\nmov.b64 da, {%44, 0x80000020};\nmov.b64 db, {%45, 0x80000020};\n"
        "wgmma.mma_async.sync.aligned.m64n88k16.f32.bf16.bf16 {%0,%1,%2,%3,%4,%5,%6,%7,%8,%9,%10,%11,%12,%13,%14,%15,%16,%17,%18,%19,%20,%21,%22,%23,%24,%25,%26,%27,%28,%29,%30,%31,%32,%33,%34,%35,%36,%37,%38,%39,%40,%41,%42,%43}, da, db, p, 1, 1, 1, 0;\n}"
        : "+f"(d[0]), "+f"(d[1]), "+f"(d[2]), "+f"(d[3]), "+f"(d[4]), "+f"(d[5]), "+f"(d[6]), "+f"(d[7]), "+f"(d[8]), "+f"(d[9]), "+f"(d[10]), "+f"(d[11]), "+f"(d[12]), "+f"(d[13]), "+f"(d[14]), "+f"(d[15]), "+f"(d[16]), "+f"(d[17]), "+f"(d[18]), "+f"(d[19]), "+f"(d[20]), "+f"(d[21]), "+f"(d[22]), "+f"(d[23]), "+f"(d[24]), "+f"(d[25]), "+f"(d[26]), "+f"(d[27]), "+f"(d[28]), "+f"(d[29]), "+f"(d[30]), "+f"(d[31]), "+f"(d[32]), "+f"(d[33]), "+f"(d[34]), "+f"(d[35]), "+f"(d[36]), "+f"(d[37]), "+f"(d[38]), "+f"(d[39]), "+f"(d[40]), "+f"(d[41]), "+f"(d[42]), "+f"(d[43])
        : "r"(da), "r"(db), "r"(acc));
}
__device__ __forceinline__ void wgmma_rs_n88(float (&d)[44], const uint32_t (&a)[4], uint32_t db, uint32_t acc = 1) {
    asm volatile("{\n.reg .b64 db;\n.reg .pred p;\nsetp.ne.u32 p, %49, 0;\nmov.b64 db, {%48, 0x80000020};\n"
        "wgmma.mma_async.sync.aligned.m64n88k16.f32.bf16.bf16 {%0,%1,%2,%3,%4,%5,%6,%7,%8,%9,%10,%11,%12,%13,%14,%15,%16,%17,%18,%19,%20,%21,%22,%23,%24,%25,%26,%27,%28,%29,%30,%31,%32,%33,%34,%35,%36,%37,%38,%39,%40,%41,%42,%43}, {%44,%45,%46,%47}, db, p, 1, 1, 0;\n}"
        : "+f"(d[0]), "+f"(d[1]), "+f"(d[2]), "+f"(d[3]), "+f"(d[4]), "+f"(d[5]), "+f"(d[6]), "+f"(d[7]), "+f"(d[8]), "+f"(d[9]), "+f"(d[10]), "+f"(d[11]), "+f"(d[12]), "+f"(d[13]), "+f"(d[14]), "+f"(d[15]), "+f"(d[16]), "+f"(d[17]), "+f"(d[18]), "+f"(d[19]), "+f"(d[20]), "+f"(d[21]), "+f"(d[22]), "+f"(d[23]), "+f"(d[24]), "+f"(d[25]), "+f"(d[26]), "+f"(d[27]), "+f"(d[28]), "+f"(d[29]), "+f"(d[30]), "+f"(d[31]), "+f"(d[32]), "+f"(d[33]), "+f"(d[34]), "+f"(d[35]), "+f"(d[36]), "+f"(d[37]), "+f"(d[38]), "+f"(d[39]), "+f"(d[40]), "+f"(d[41]), "+f"(d[42]), "+f"(d[43])
        : "r"(a[0]), "r"(a[1]), "r"(a[2]), "r"(a[3]), "r"(db), "r"(acc));
}
__device__ __forceinline__ float tanh_fast(float x) { float y; asm("tanh.approx.f32 %0, %1;" : "=f"(y) : "f"(x)); return y; }
__device__ __forceinline__ uint32_t pack_bf16(float lo, float hi) { uint32_t r; asm("cvt.rn.bf16x2.f32 %0, %1, %2;" : "=r"(r) : "f"(hi), "f"(lo)); return r; }
__device__ __forceinline__ uint32_t badd(uint32_t a, uint32_t b) { uint32_t r; asm("add.rn.bf16x2 %0, %1, %2;" : "=r"(r) : "r"(a), "r"(b)); return r; }
__device__ __forceinline__ uint32_t vbadd(uint32_t a, uint32_t b) { uint32_t r; asm volatile("add.rn.bf16x2 %0, %1, %2;" : "=r"(r) : "r"(a), "r"(b)); return r; }
__device__ __forceinline__ uint32_t vbfma(uint32_t a, uint32_t b, uint32_t c) { uint32_t r; asm volatile("fma.rn.bf16x2 %0, %1, %2, %3;" : "=r"(r) : "r"(a), "r"(b), "r"(c)); return r; }
__device__ __forceinline__ uint32_t bsub(uint32_t a, uint32_t b) { uint32_t r; asm("sub.rn.bf16x2 %0, %1, %2;" : "=r"(r) : "r"(a), "r"(b)); return r; }
__device__ __forceinline__ uint32_t bfma(uint32_t a, uint32_t b, uint32_t c) { uint32_t r; asm("fma.rn.bf16x2 %0, %1, %2, %3;" : "=r"(r) : "r"(a), "r"(b), "r"(c)); return r; }
constexpr uint32_t BF_2 = 0x40004000u, BF_M2 = 0xC000C000u, BF_M3 = 0xC040C040u, BF_4 = 0x40804080u;

__device__ __forceinline__ void emit_phase(const float (&y)[44], float sc, float of, uint32_t os_lane, uint32_t os_row, int bar,
                                           __nv_bfloat16* __restrict__ orow, int nq) {
    uint32_t r[22];
#pragma unroll
    for (int i = 0; i < 22; i++) r[i] = pack_bf16(fmaf(tanh_fast(y[2 * i]), sc, of), fmaf(tanh_fast(y[2 * i + 1]), sc, of));
#pragma unroll
    for (int g2 = 0; g2 < 5; g2++) stsm4t(os_lane + g2 * 16 * EP, r[4 * g2], r[4 * g2 + 1], r[4 * g2 + 2], r[4 * g2 + 3]);
    stsm4t(os_lane + 5 * 16 * EP, r[20], r[21], 0u, 0u);
    asm volatile("bar.sync %0, 128;" ::"r"(bar) : "memory");
    uint4 f[3], g[3];
#pragma unroll
    for (int p = 0; p < 3; p++) { f[p] = lds128(os_row + p * 32 * EP); g[p] = lds128(os_row + 96 * EP + p * 32 * EP); }
#pragma unroll
    for (int p = 0; p < 3; p++) {
        uint4 v;
        asm("mul.rn.bf16x2 %0, %1, %2;" : "=r"(v.x) : "r"(f[p].x), "r"(g[p].x));
        asm("mul.rn.bf16x2 %0, %1, %2;" : "=r"(v.y) : "r"(f[p].y), "r"(g[p].y));
        asm("mul.rn.bf16x2 %0, %1, %2;" : "=r"(v.z) : "r"(f[p].z), "r"(g[p].z));
        asm("mul.rn.bf16x2 %0, %1, %2;" : "=r"(v.w) : "r"(f[p].w), "r"(g[p].w));
        if (p * 32 < nq) *reinterpret_cast<uint4*>(orow + p * 32 * 6 * DCH) = v;
    }
}
__device__ __forceinline__ void cluster_sync_() {
    __syncwarp();
    asm volatile("barrier.cluster.arrive.relaxed.aligned;\nbarrier.cluster.wait.aligned;" ::: "memory");
}
__device__ __forceinline__ void xform_item(const uint4 (&e)[5], uint32_t (&u)[5][4]) {
#pragma unroll
    for (int v = 0; v < 4; v++) {
        const uint32_t e0 = (&e[0].x)[v], e1 = (&e[1].x)[v], e2 = (&e[2].x)[v], e3 = (&e[3].x)[v], e4 = (&e[4].x)[v];
        const uint32_t u3 = bsub(e3, e1);
        u[3][v] = u3;
        u[0][v] = bfma(BF_2, bsub(e0, e2), u3);
        u[1][v] = bfma(BF_M2, e1, bsub(e3, e2));
        u[2][v] = bfma(BF_M3, e2, bfma(BF_2, e1, e3));
        u[4][v] = bfma(BF_M2, u3, bsub(e4, e2));
    }
}

__global__ void __launch_bounds__(256, 1)
conv_kernel(const __grid_constant__ CUtensorMap tmx2, const __grid_constant__ CUtensorMap tm3,
            const __grid_constant__ CUtensorMap tm6, uint8_t* __restrict__ scratch, __nv_bfloat16* __restrict__ out) {
    extern __shared__ __align__(1024) uint8_t smem_raw[];
    const uint32_t sbase = smem_u32(smem_raw);
    const uint32_t as = sbase, ws = sbase + OFF_W, os = ws, es = sbase + OFF_E, bars = sbase + OFF_B;
    const uint32_t wfull = bars, wempty = bars + 32, afull = bars + 64, aempty = bars + 96, rfull = bars + 128, w0full = bars + 136;

    const int half = blockIdx.x & 1, seq = (blockIdx.x >> 1) & 3, ct = blockIdx.x >> 3;
    const int b = seq >> 1, phase = seq & 1;
    const int s_start = half * (3 * TRI) - 14;
    const int crot = ct & ~1;
    if (threadIdx.x == 224) {
        mbar_init(rfull, 1);
        mbar_expect_tx(rfull, EXBYTES);
        tma_4d(es, &tmx2, crot * 32, phase, s_start, b, rfull);
        tma_4d(es + RBOX2 * 128, &tmx2, crot * 32, phase, s_start + RBOX2, b, rfull);
        asm volatile("fence.mbarrier_init.release.cluster;" ::: "memory");
    }
    if (threadIdx.x == 160) {
        mbar_init(w0full, 1);
        mbar_expect_tx(w0full, 12288);
        tma_3d(ws, &tm3, ct * 32, crot * 32, 0, w0full);
        tma_3d(ws + 18432, &tm3, ct * 32 + DCH, crot * 32, 0, w0full);
        asm volatile("fence.mbarrier_init.release.cluster;" ::: "memory");
    }
    const int warp = __shfl_sync(0xffffffffu, threadIdx.x >> 5, 0), lane = threadIdx.x & 31;
    const int grp = blockIdx.x & 7;
    const int wcol = ct * 32 + half * DCH;
    uint8_t* gimg = scratch + grp * GRP_BYTES;
    unsigned int* ready = reinterpret_cast<unsigned int*>(gimg + NCHUNK * XABYTES);
    const int q0 = threadIdx.x >> 2, col = threadIdx.x & 3;
    if (warp == 6) {
        if (elect_one()) {
            asm volatile("prefetch.tensormap [%0];" ::"l"(&tm6) : "memory");
            if ((sbase & 0xFFFFFFu) != SB) __trap();
#pragma unroll 1
            for (int i = 0; i < 16; i++) mbar_init(bars + 8 * i, (i & 4) == 0 ? 1 : i < 8 ? 16 : 4);
            for (int i = 0; i < 4; i++) mbar_arrive(afull + 8 * i);
            asm volatile("fence.mbarrier_init.release.cluster;" ::: "memory");
        }
        __syncwarp();
    }
    cluster_sync_();
    if (warp == 6) {
        if (elect_one()) {
            mbar_expect_tx(wfull, WABYTES - 12288);
            tma_3d_mc(ws + half * 18432 + 6144, &tm6, wcol, crot * 32, 3, wfull, (uint16_t)3);
            mbar_expect_tx(wfull + 8, WBBYTES);
            tma_3d_mc(ws + WABYTES + half * 12288, &tm6, wcol, crot * 32, 9, wfull + 8, (uint16_t)3);
            mbar_expect_tx(wfull + 16, WABYTES);
            tma_3d_mc(ws + WCBYTES + half * 18432, &tm3, wcol, crot * 32 + 32, 0, wfull + 16, (uint16_t)3);
            tma_3d_mc(ws + WCBYTES + half * 18432 + 6144, &tm6, wcol, crot * 32 + 32, 3, wfull + 16, (uint16_t)3);
            mbar_expect_tx(wfull + 24, WBBYTES);
            tma_3d_mc(ws + WCBYTES + WABYTES + half * 12288, &tm6, wcol, crot * 32 + 32, 9, wfull + 24, (uint16_t)3);
        }
        __syncwarp();
    }
    unsigned int epoch = 0;
    if (warp == 2 || warp == 3) epoch = *(volatile unsigned int*)&ready[ct] + 1;
    mbar_wait(rfull, 0);
#pragma unroll 1
    for (int i = q0; i < 2 * 92; i += 64) {
        const int k = i >= 92, q = i - 92 * k;
        uint4 e[5];
#pragma unroll
        for (int r = 0; r < 5; r++) e[r] = lds128(es + (3 * q + r) * 128 + (((k * 4 + col) ^ ((3 * q + r) & 7)) << 4));
        uint32_t u[5][4];
        xform_item(e, u);
        const uint32_t io = q * 64 + ((col ^ ((q >> 1) & 3)) << 4);
#pragma unroll
        for (int a = 0; a < 5; a++) sts128(as + k * XABYTES + io + a * ABYTES, u[a][0], u[a][1], u[a][2], u[a][3]);
    }
    asm volatile("fence.proxy.async.shared::cta;" ::: "memory");
    asm volatile("bar.sync 1, 256;" ::: "memory");
    if (warp == 3) {
        if (elect_one()) {
            asm volatile("cp.async.bulk.global.shared::cta.bulk_group [%0], [%1], %2;"
                         ::"l"(gimg + (size_t)ct * XABYTES), "r"(as + (ct & 1) * XABYTES), "r"(XABYTES) : "memory");
            asm volatile("cp.async.bulk.commit_group;" ::: "memory");
        }
        __syncwarp();
    }
    const int w4 = warp & 3;
    uint32_t wempty_c;
    asm("mapa.shared::cluster.u32 %0, %1, %2;" : "=r"(wempty_c) : "r"(wempty), "r"(lane & 1));
    mbar_wait(w0full, 0);
#define EPI_SETUP \
    const int qr = (threadIdx.x & 127) >> 2; \
    __nv_bfloat16* orow = out + ((size_t)b * T_LEN + 2 * (half * (3 * TRI) + 3 * qr) + phase) * DCH + ct * 32 + col * 8; \
    const uint32_t os_lane = os + ((w4 >> 1) * 96 + (lane >> 4) * 8 + (lane & 7)) * EP + (w4 & 1) * 32 + ((lane >> 3) & 1) * 16; \
    const uint32_t os_row = os + qr * EP + col * 16; \
    const uint32_t ex = es + (threadIdx.x & 127) * 16; \
    const float asc = (w4 >> 1) ? 0.5f : 1.f, aof = (w4 >> 1) ? 0.5f : 0.f;
    if (warp < 4) {
        float m0[44];
#define WGY_STAGE(P, j, A) \
                wgmma_ss_n88(m0, desc_a(P, 3 * j, 0), desc_b(P * XABYTES + j * 64), A); \
                wgmma_ss_n88(m0, desc_a(P, 3 * j, 1), desc_b(P * XABYTES + j * 64 + 32));
        auto duties_a = [&](int c) {
            const int cp = c & 1, ppar = ((c - 1) >> 1) & 1;
            const uint32_t obo = 16 - cp * 16, ows = ws + (cp ^ 1) * WCBYTES;
            const int cn = c - 1 < crot ? c - 1 : c + 1;
            if (lane < 2) mbar_arrive_addr(wempty_c + obo + 8);
            if (lane == 2) mbar_arrive(aempty + 8 * (cp ^ 1));
            if (warp == 0) {
                mbar_wait_fast(wempty + obo, ppar);
                if (elect_one()) {
                    mbar_expect_tx(wfull + obo, WABYTES);
                    tma_3d_mc(ows + half * 18432, &tm3, wcol, cn * 32, 0, wfull + obo, (uint16_t)3);
                    tma_3d_mc(ows + half * 18432 + 6144, &tm6, wcol, cn * 32, 3, wfull + obo, (uint16_t)3);
                }
            } else if (warp >= 2) {
                if (c == 1) {
                    if (lane < NCHUNK) flag_wait(&ready[lane], epoch);
                    __syncwarp();
                    asm volatile("fence.proxy.async.global;" ::: "memory");
                }
                const int g = warp - 2;
                const uint32_t aoff = (cp ^ 1) * 8 + g * 16;
                mbar_wait_fast(aempty + aoff, ppar);
                if (elect_one()) {
                    mbar_expect_tx(afull + aoff, (1 + 3 * g) * ABYTES);
                    bulk_load(as + (cp ^ 1) * XABYTES + g * ABYTES, gimg + (size_t)cn * XABYTES + g * ABYTES,
                              (1 + 3 * g) * ABYTES, afull + aoff);
                }
            }
        };
        auto duties_b = [&](int c) {
            const int cp = c & 1, ppar = ((c - 1) >> 1) & 1;
            const uint32_t obo = 16 - cp * 16, ows = ws + (cp ^ 1) * WCBYTES;
            const int cn = c - 1 < crot ? c - 1 : c + 1;
            mbar_wait_fast(wempty + obo + 8, ppar);
            if (elect_one()) {
                mbar_expect_tx(wfull + obo + 8, WBBYTES);
                tma_3d_mc(ows + WABYTES + half * 12288, &tm6, wcol, cn * 32, 9, wfull + obo + 8, (uint16_t)3);
            }
        };
#pragma unroll 1
        for (int c = 0; c < NCHUNK - 2; c++) {
            const int cp = c & 1, par = (c >> 1) & 1;
            const uint32_t bo = cp * 16;
            mbar_wait_fast2(wfull + bo, afull + 8 * cp, par);
            if (cp) { wgmma_fence(); WGY_STAGE(1, 0, 1) WGY_STAGE(1, 1, 1) WGY_STAGE(1, 2, 1) wgmma_commit(); }
            else    { wgmma_fence(); WGY_STAGE(0, 0, c) WGY_STAGE(0, 1, 1) WGY_STAGE(0, 2, 1) wgmma_commit(); }
            wgmma_wait<1>();
            if (c >= 1) duties_a(c);
            __syncwarp();
            mbar_wait_fast(wfull + bo + 8, par);
            if (cp) { wgmma_fence(); WGY_STAGE(1, 3, 1) WGY_STAGE(1, 4, 1) wgmma_commit(); }
            else    { wgmma_fence(); WGY_STAGE(0, 3, 1) WGY_STAGE(0, 4, 1) wgmma_commit(); }
            wgmma_wait<1>();
            if (lane < 2) mbar_arrive_addr(wempty_c + bo);
            if (c >= 1 && warp == 0) duties_b(c);
            if (c == 0 && warp == 3 && elect_one()) {
                asm volatile("cp.async.bulk.wait_group 0;" ::: "memory");
                asm volatile("fence.acq_rel.gpu;" ::: "memory");
                asm volatile("st.relaxed.gpu.global.u32 [%0], %1;" ::"l"(&ready[ct]), "r"(epoch) : "memory");
            }
            __syncwarp();
        }
        wgmma_wait<0>();
        duties_a(NCHUNK - 2);
        if (warp == 1) duties_b(NCHUNK - 2);
        __syncwarp();
        EPI_SETUP
        mbar_wait_fast2(wfull, wfull + 8, 1);
        mbar_wait_fast2(wfull + 16, wfull + 24, 1);
        mbar_wait_fast2(afull, afull + 8, 1);
        asm volatile("bar.sync 4, 256;" ::: "memory");
        wgmma_fence();
        WGY_STAGE(0, 0, 1) WGY_STAGE(0, 1, 1) WGY_STAGE(0, 2, 1) WGY_STAGE(0, 3, 1) WGY_STAGE(0, 4, 1)
        WGY_STAGE(1, 0, 1) WGY_STAGE(1, 1, 1) WGY_STAGE(1, 2, 1) WGY_STAGE(1, 3, 1) WGY_STAGE(1, 4, 1)
        wgmma_commit();
        wgmma_wait<0>();
        asm volatile("bar.sync 1, 256;" ::: "memory");
#pragma unroll
        for (int i = 0; i < 11; i++) {
            const uint4 v0 = lds128(ex + i * 2048);
            m0[4 * i + 0] = fmaf(m0[4 * i + 0], 0.5f * asc, __uint_as_float(v0.x));
            m0[4 * i + 1] = fmaf(m0[4 * i + 1], 0.5f * asc, __uint_as_float(v0.y));
            m0[4 * i + 2] = fmaf(m0[4 * i + 2], 0.5f * asc, __uint_as_float(v0.z));
            m0[4 * i + 3] = fmaf(m0[4 * i + 3], 0.5f * asc, __uint_as_float(v0.w));
        }
        emit_phase(m0, asc, aof, os_lane, os_row, 2, orow, (half ? TRI - 1 : TRI) - qr);
    } else {
        const int kr = ((lane >> 4) << 3) + (lane & 7);
        const uint32_t wl = ws + kr * 64 + ((((w4 & 1) * 2 + ((lane >> 3) & 1)) ^ ((kr >> 1) & 3)) << 4);
        const uint32_t wlA = wl + (w4 >> 1) * 18432, wlB = wl + WABYTES + (w4 >> 1) * 12288 - 9 * 2048;
        float m1[44], m2[44], m3[44], m4[44];
        uint32_t gg[2][4][4], rw[3][4];
        ldsm4t(rw[0], wlA);
        ldsm4t(rw[1], wlA + 2048);
        ldsm4t(rw[2], wlA + 4096);
        uint32_t okf = 1, sv[4];
#pragma unroll
        for (int v = 0; v < 4; v++) { sv[v] = vbadd(rw[0][v], rw[2][v]); rw[0][v] = vbfma(BF_2, rw[1][v], rw[0][v]); }
#pragma unroll 1
        for (int c2 = 0; c2 < NCHUNK / 2; c2++) {
            const int par = c2 & 1;
#pragma unroll
            for (int tt = 0; tt < 20; tt++) {
                const int cp = tt / 10, t = tt % 10, j = t >> 1, kk = t & 1;
                const int c = 2 * c2 + cp;
                const uint32_t bo = cp * 16;
                const uint32_t acc = tt == 0 ? c2 : 1;
#pragma unroll
                for (int v = 0; v < 4; v++) { gg[kk][0][v] = badd(sv[v], rw[1][v]); gg[kk][1][v] = bsub(sv[v], rw[1][v]); }
#pragma unroll
                for (int v = 0; v < 4; v++) gg[kk][2][v] = bfma(BF_4, rw[2][v], rw[0][v]);
#pragma unroll
                for (int v = 0; v < 4; v++) gg[kk][3][v] = rw[2][v];
                {
                    if (t == 1 && c == 0) mbar_wait(wfull, 0);
                    if (t == 5 && !okf) mbar_wait(wfull + bo + 8, par);
                    if (t == 9 && !okf && c + 1 < NCHUNK) mbar_wait(wfull + 16 - bo, cp ? par ^ 1 : par);
                    const uint32_t na = t == 9 ? wlA + (cp ^ 1) * WCBYTES : (t + 1 < 6 ? wlA : wlB) + cp * WCBYTES + ((t + 1) >> 1) * 6144 + ((t + 1) & 1) * 1024;
                    ldsm4t(rw[0], na);
                    ldsm4t(rw[1], na + 2048);
                    ldsm4t(rw[2], na + 4096);
                }
                if (t == 0 && !okf) mbar_wait(afull + 16 + 8 * cp, par);
                wgmma_fence();
                wgmma_rs_n88(m1, gg[kk][0], desc_b(cp * XABYTES + j * 64 + kk * 32 + 1 * ABYTES), acc);
                wgmma_rs_n88(m2, gg[kk][1], desc_b(cp * XABYTES + j * 64 + kk * 32 + 2 * ABYTES), acc);
                wgmma_rs_n88(m3, gg[kk][2], desc_b(cp * XABYTES + j * 64 + kk * 32 + 3 * ABYTES), acc);
                wgmma_rs_n88(m4, gg[kk][3], desc_b(cp * XABYTES + j * 64 + kk * 32 + 4 * ABYTES), acc);
                wgmma_commit();
                if (t == 4) okf = mbar_try(wfull + bo + 8, par);
                if (t == 8) okf = mbar_try(wfull + 16 - bo, cp ? par ^ 1 : par) & mbar_try(afull + 24 - 8 * cp, cp ? par ^ 1 : par);
                if ((t == 5 || t == 9) && lane < 2 && c + 2 < NCHUNK) mbar_arrive_addr(wempty_c + bo + (t == 9 ? 8 : 0));
#pragma unroll
                for (int v = 0; v < 4; v++) { sv[v] = vbadd(rw[0][v], rw[2][v]); rw[0][v] = vbfma(BF_2, rw[1][v], rw[0][v]); }
                wgmma_wait<1>();
                if (t == 0 && c > 0 && lane == 0) mbar_arrive(aempty + 16 + 8 * (cp ^ 1));
            }
        }
        asm volatile("bar.arrive 4, 256;" ::: "memory");
        EPI_SETUP
        wgmma_wait<0>();
#pragma unroll
        for (int i = 0; i < 11; i++) {
            float y[4];
#pragma unroll
            for (int v = 0; v < 4; v++) {
                m1[4 * i + v] = fmaf(m2[4 * i + v], asc * (-1.f / 6.f), (-0.5f * asc) * m1[4 * i + v]);
                y[v] = fmaf(m3[4 * i + v], asc * (1.f / 6.f), m1[4 * i + v]);
            }
            sts128(ex + i * 2048, __float_as_uint(y[0]), __float_as_uint(y[1]), __float_as_uint(y[2]), __float_as_uint(y[3]));
        }
        asm volatile("bar.arrive 1, 256;" ::: "memory");
#pragma unroll
        for (int i = 0; i < 44; i++) m2[i] = fmaf(m2[i] + m3[i], asc * (1.f / 3.f), m1[i]);
        asm volatile("bar.sync 3, 128;" ::: "memory");
        emit_phase(m2, asc, aof, os_lane - OFF_W + ABYTES, os_row - OFF_W + ABYTES, 3, orow + 2 * DCH, (half ? TRI - 1 : TRI) - qr);
#pragma unroll
        for (int i = 0; i < 44; i++) m4[i] = fmaf(m4[i], asc, fmaf(m3[i], asc * (2.f / 3.f), m1[i]));
        emit_phase(m4, asc, aof, os_lane - OFF_W + XABYTES + ABYTES, os_row - OFF_W + XABYTES + ABYTES, 3, orow + 4 * DCH, (half ? TRI - 2 : TRI) - qr);
    }
}

__global__ void __launch_bounds__(256)
conv_simple(const __nv_bfloat16* __restrict__ x, const __nv_bfloat16* __restrict__ w, __nv_bfloat16* __restrict__ out) {
    __shared__ float xs[8][DCH];
    const int d = blockIdx.x * 256 + threadIdx.x, t0 = blockIdx.y * 8, b = blockIdx.z;
    float f[8] = {}, g[8] = {};
    for (int i = 0; i < 15; i++) {
        __syncthreads();
        for (int e = threadIdx.x; e < 8 * DCH; e += 256) {
            const int ts = t0 + (e >> 9) + 2 * i - 28;
            xs[e >> 9][e & 511] = ts >= 0 ? __bfloat162float(x[((size_t)b * T_LEN + ts) * DCH + (e & 511)]) : 0.f;
        }
        __syncthreads();
        const __nv_bfloat16* wr = w + (size_t)i * DCH * 2 * DCH + d;
        for (int c = 0; c < DCH; c++) {
            const float wf = __bfloat162float(wr[(size_t)c * 2 * DCH]), wg = __bfloat162float(wr[(size_t)c * 2 * DCH + DCH]);
#pragma unroll
            for (int r = 0; r < 8; r++) { f[r] = fmaf(xs[r][c], wf, f[r]); g[r] = fmaf(xs[r][c], wg, g[r]); }
        }
    }
#pragma unroll
    for (int r = 0; r < 8; r++) out[((size_t)b * T_LEN + t0 + r) * DCH + d] = __float2bfloat16(tanhf(f[r]) / (1.f + expf(-g[r])));
}

typedef CUresult (*EncodeFn)(CUtensorMap*, CUtensorMapDataType, cuuint32_t, void*, const cuuint64_t*, const cuuint64_t*, const cuuint32_t*,
                             const cuuint32_t*, CUtensorMapInterleave, CUtensorMapSwizzle, CUtensorMapL2promotion, CUtensorMapFloatOOBfill);
}

extern "C" void kernel_launch(void* const* d_in, const int* in_sizes, int n_in, void* d_out, int out_size) {
    static EncodeFn enc = nullptr;
    static uint8_t* scratch = nullptr;
    static bool resident = false;
    cudaLaunchConfig_t cfg = {};
    cfg.gridDim = dim3(128);
    cfg.blockDim = dim3(256);
    cfg.dynamicSmemBytes = SMEM_BYTES;
    cfg.stream = cudaStreamPerThread;
    cudaLaunchAttribute at[1];
    at[0].id = cudaLaunchAttributeClusterDimension;
    at[0].val.clusterDim.x = 2; at[0].val.clusterDim.y = 1; at[0].val.clusterDim.z = 1;
    cfg.attrs = at;
    cfg.numAttrs = 1;
    if (!scratch) {
        void* fn = nullptr;
        cudaDriverEntryPointQueryResult qr;
        cudaGetDriverEntryPoint("cuTensorMapEncodeTiled", &fn, cudaEnableDefault, &qr);
        enc = (EncodeFn)fn;
        void* p = nullptr;
        cudaGetSymbolAddress(&p, g_scratch);
        scratch = (uint8_t*)(((uintptr_t)p + (2u << 20) - 1) & ~(uintptr_t)((2u << 20) - 1));
        cudaFuncSetAttribute(conv_kernel, cudaFuncAttributeMaxDynamicSharedMemorySize, SMEM_BYTES);
        int nclusters = 0;
        resident = enc && cudaOccupancyMaxActiveClusters(&nclusters, conv_kernel, &cfg) == cudaSuccess && nclusters >= 64;
    }
    if (!resident) {
        conv_simple<<<dim3(DCH / 256, T_LEN / 8, 2), 256, 0, cudaStreamPerThread>>>((const __nv_bfloat16*)d_in[0], (const __nv_bfloat16*)d_in[1],
                                                                                     (__nv_bfloat16*)d_out);
        return;
    }
    CUtensorMap tmx2, tm3, tm6;
    {
        cuuint64_t dims[4] = {DCH, 2, T_LEN / 2, 2};
        cuuint64_t strides[3] = {DCH * 2, DCH * 4, (cuuint64_t)DCH * T_LEN * 2};
        cuuint32_t box[4] = {64, 1, RBOX2, 1};
        cuuint32_t es[4] = {1, 1, 1, 1};
        enc(&tmx2, CU_TENSOR_MAP_DATA_TYPE_BFLOAT16, 4, d_in[0], dims, strides, box, es, CU_TENSOR_MAP_INTERLEAVE_NONE,
            CU_TENSOR_MAP_SWIZZLE_128B, CU_TENSOR_MAP_L2_PROMOTION_L2_128B, CU_TENSOR_MAP_FLOAT_OOB_FILL_NONE);
    }
    for (int k = 0; k < 2; k++) {
        cuuint64_t dims[3] = {2 * DCH, DCH, 15};
        cuuint64_t strides[2] = {2 * DCH * 2, (cuuint64_t)2 * DCH * DCH * 2};
        cuuint32_t box[3] = {32, 32, k ? 6u : 3u};
        cuuint32_t es[3] = {1, 1, 1};
        enc(k ? &tm6 : &tm3, CU_TENSOR_MAP_DATA_TYPE_BFLOAT16, 3, d_in[1], dims, strides, box, es, CU_TENSOR_MAP_INTERLEAVE_NONE,
            CU_TENSOR_MAP_SWIZZLE_64B, CU_TENSOR_MAP_L2_PROMOTION_L2_128B, CU_TENSOR_MAP_FLOAT_OOB_FILL_NONE);
    }
    cudaLaunchKernelEx(&cfg, conv_kernel, tmx2, tm3, tm6, scratch, (__nv_bfloat16*)d_out);
}
```
